```python
import torch

def _softmax(x, axis=-1):
    return torch.softmax(x, dim=axis)
def _gelu(x):
    return torch.nn.functional.gelu(x, approximate="tanh")
def _silu(x):
    return torch.nn.functional.silu(x)
def _sigmoid(x):
    return torch.sigmoid(x)
def _layernorm(x, axis=-1, eps=1e-5):
    m = x.mean(dim=axis, keepdim=True)
    v = x.var(dim=axis, keepdim=True, unbiased=False)
    return (x - m) / torch.sqrt(v + eps)
def _scatter_add(tgt, idx, src, axis=0):
    return tgt.clone().index_add_(axis, idx, src)
def _segment_sum(src, seg, n):
    out = torch.zeros((n,) + src.shape[1:], dtype=src.dtype)
    return out.index_add_(0, seg, src)
def _pad(x, pw):
    flat = tuple(v for pair in reversed(pw) for v in pair)
    return torch.nn.functional.pad(x, flat)

kernel_name = 'gated_mix__sliding_local_dilated__mixer_token_mlp__prompt'

def setup_inputs():

    _w = (lambda a: (lambda t: t.to(torch.bfloat16) if t.is_floating_point() else t)(torch.as_tensor(a)))
    def _A_setup():
        B, S, D = 1, 2048, 640
        return {
            "x": _w((lambda *s: torch.randn(*s, dtype=torch.bfloat16) * 0.05)(B, S, D)),
            "wqkv": _w((lambda *s: torch.randn(*s, dtype=torch.bfloat16) * 0.8)(D, 3 * D)),
            "wo": _w((lambda *s: torch.randn(*s, dtype=torch.bfloat16) * 0.05)(D, D)),
        }
    _A_in = _A_setup()

    def _B_setup():
        B, S, D, F = 1, 2048, 640, 1536
        return {
            "x": _w((lambda *s: torch.randn(*s, dtype=torch.bfloat16) * 0.05)(B, S, D)),
            "w1": _w((lambda *s: torch.randn(*s, dtype=torch.bfloat16) * 0.8)(S, F) * (S ** -0.5)),
            "b1": _w((lambda *s: torch.randn(*s, dtype=torch.bfloat16) * 0.8)(F) * 0.02),
            "w2": _w((lambda *s: torch.randn(*s, dtype=torch.bfloat16) * 0.8)(F, S) * (F ** -0.5)),
            "b2": _w((lambda *s: torch.randn(*s, dtype=torch.bfloat16) * 0.8)(S) * 0.02),
        }
    _B_in = _B_setup()

    return {
        "A_x": _A_in["x"],
        "A_wqkv": _A_in["wqkv"],
        "A_wo": _A_in["wo"],
        "B_x": _B_in["x"],
        "B_w1": _B_in["w1"],
        "B_b1": _B_in["b1"],
        "B_w2": _B_in["w2"],
        "B_b2": _B_in["b2"],
        "gate_w": _w((lambda *s: torch.randn(*s, dtype=torch.bfloat16) * 0.05)(640) * 16.0),
    }

def reference(A_x, A_wqkv, A_wo, B_x, B_w1, B_b1, B_w2, B_b2, gate_w):
    def _A_ref(x, wqkv, wo):
        B, S, D = x.shape
        H = 32; Dh = D // H
        W, dil = 8, 2
        qkv = (lambda x, *d: x.permute(*d))((x @ wqkv).reshape(B, S, 3, H, Dh), 2, 0, 3, 1, 4)
        q, k, v = qkv[0], qkv[1], qkv[2]
        scale = Dh ** -0.5
        pos = torch.arange(S)
        off = torch.arange(W) * dil
        idx = pos[:, None] - off[None, :]
        mask = idx >= 0
        idx_c = torch.where(mask, idx, 0).reshape(-1)
        kg = k[:, :, idx_c, :].reshape(B, H, S, W, Dh)
        vg = v[:, :, idx_c, :].reshape(B, H, S, W, Dh)
        logits = torch.einsum("bhsd,bhswd->bhsw", q, kg) * scale
        logits = torch.where(mask[None, None, :, :], logits, -1e9)
        attn = _softmax(logits, axis=-1)
        o = torch.einsum("bhsw,bhswd->bhsd", attn, vg)
        return (lambda x, *d: x.permute(*d))(o, 0, 2, 1, 3).reshape(B, S, D) @ wo

    def _B_ref(x, w1, b1, w2, b2):
        B, S, D = x.shape
        h = _layernorm(x, axis=-1)
        u = torch.einsum("bsd,sf->bdf", h, w1) + b1
        u = _gelu(u)
        y = torch.einsum("bdf,fs->bds", u, w2) + b2
        return (lambda x, *d: x.permute(*d))(y, 0, 2, 1)

    x = A_x
    g = _sigmoid((x * gate_w).sum(-1, keepdims=True))
    a = _A_ref(x, A_wqkv, A_wo)
    b = _B_ref(x, B_w1, B_b1, B_w2, B_b2)
    return g * a + (1 - g) * b
```

```cpp
#include <cuda_runtime.h>
#include <cuda.h>
#include <cuda_bf16.h>
#include <stdint.h>

namespace {

constexpr int S_ = 2048, D_ = 640, F_ = 1536, KCAT = D_ + F_;
constexpr int NCTA = 128, NTHREADS = 512;

constexpr int G1_STAGE = 47104;
constexpr int G2_SLOT = 24576;
__host__ __device__ constexpr int g2_slot(int i) { return 18 * 1024 + ((i + 7) & 7) * G2_SLOT; }
constexpr int P2_SLOT = 26624;
constexpr int P2N = 7;
constexpr int GW_OFF = 184 * 1024;
constexpr int XROW_OFF = 186 * 1024;
constexpr int XCH_OFF = 210 * 1024;
constexpr int OSTG_OFF = 190 * 1024;
constexpr int BAR_OFF = 226 * 1024;
constexpr int GV_OFF = BAR_OFF + 512;
constexpr int SMEM_BYTES = 227 * 1024;

#define G1D 1100
#define G1D2 2150
#define G1D3 2600
#define PREP_KB 3
#define PREP2_KB 5
#define PF1_0 4800
#define PF1_P 550
#define W10 0
#define W1E 12
#define W1A 7
#define SYNC_KB 3
#define SYNC_D 900
#define SYNC_G 200
#define SYNC_NS 2350
#define G2P 260
#define FILL4 1100
#define FILL6 1620
#define GO_CLK 1800
#define SCHED_R 4
#define IDLE_CLK 11000
#define XCH0 5000
#define XCHP 100
#define XCH1 6100
#define ODELAY 100
#define PACE 400
#define OPOLL 5200
#define WOP 300
#define HP 160
#define H0POLL 0
#define HI 3
#define ATF 1
#define OAFT 0
#define U1W 0
#define UCH 8
#define XCH2 XCH1
#define U1POLL 1300
#define U1D 0

struct Scratch {
  unsigned sync[8 * 32];
  float gate[S_ * 4];
  uint4 halo[16 * 8 * 2 * 224];
  __nv_bfloat16 h[S_ * D_];
  __nv_bfloat16 o[S_ * D_];
  __nv_bfloat16 bcat[D_ * KCAT];
};
__device__ __align__(1024) Scratch g_scr;
#define PROF_T(i) do {} while (0)
#define PROF_W(i, c) do {} while (0)

struct Maps { CUtensorMap x, wa, wb, h, w1, bc, w2, ust, outa, outb, wo, woa, wob; };

__device__ __forceinline__ void mbar_init(uint32_t bar, uint32_t cnt) { asm volatile("mbarrier.init.shared::cta.b64 [%0], %1;" :: "r"(bar), "r"(cnt)); }
__device__ __forceinline__ void mbar_expect_tx(uint32_t bar, uint32_t bytes) { asm volatile("mbarrier.arrive.expect_tx.shared::cta.b64 _, [%0], %1;" :: "r"(bar), "r"(bytes) : "memory"); }
__device__ __forceinline__ void mbar_wait(uint32_t bar, uint32_t parity) {
  asm volatile("{\n.reg .pred p;\n.reg .u32 c;\nmov.u32 c, 0;\nLAB_WAIT:\n"
               "mbarrier.try_wait.parity.shared::cta.b64 p, [%0], %1;\n@p bra LAB_DONE;\n"
               "add.u32 c, c, 1;\nsetp.lt.u32 p, c, 0x100000;\n@p bra LAB_WAIT;\ntrap;\nLAB_DONE:\n}" :: "r"(bar), "r"(parity) : "memory");
}
__device__ __forceinline__ void mbar_arrive_if(uint32_t bar, bool pred) {
  asm volatile("{\n.reg .pred p;\nsetp.ne.b32 p, %1, 0;\n@p mbarrier.arrive.shared::cta.b64 _, [%0];\n}" :: "r"(bar), "r"((int)pred) : "memory");
}
__device__ __forceinline__ void tma2(uint32_t dst, const CUtensorMap* m, int c0, int c1, uint32_t bar) {
  asm volatile("cp.async.bulk.tensor.2d.shared::cluster.global.mbarrier::complete_tx::bytes [%0], [%1, {%3, %4}], [%2];"
               :: "r"(dst), "l"(m), "r"(bar), "r"(c0), "r"(c1) : "memory");
}
__device__ __forceinline__ void tma3(uint32_t dst, const CUtensorMap* m, int c0, int c1, int c2, uint32_t bar) {
  asm volatile("cp.async.bulk.tensor.3d.shared::cluster.global.mbarrier::complete_tx::bytes [%0], [%1, {%3, %4, %5}], [%2];"
               :: "r"(dst), "l"(m), "r"(bar), "r"(c0), "r"(c1), "r"(c2) : "memory");
}
__device__ __forceinline__ void tma_store2(const CUtensorMap* m, uint32_t src, int c0, int c1) {
  asm volatile("cp.async.bulk.tensor.2d.global.shared::cta.bulk_group [%0, {%2, %3}], [%1];" :: "l"(m), "r"(src), "r"(c0), "r"(c1) : "memory");
}
__device__ __forceinline__ void tma_store3(const CUtensorMap* m, uint32_t src, int c0, int c1, int c2) {
  asm volatile("cp.async.bulk.tensor.3d.global.shared::cta.bulk_group [%0, {%2, %3, %4}], [%1];" :: "l"(m), "r"(src), "r"(c0), "r"(c1), "r"(c2) : "memory");
}
__device__ __forceinline__ void stg32(void* p, uint32_t v) { asm volatile("st.global.u32 [%0], %1;" :: "l"(p), "r"(v) : "memory"); }
__device__ __forceinline__ void bulk_load(uint32_t dst, const void* src, uint32_t bytes, uint32_t bar) {
  asm volatile("cp.async.bulk.shared::cluster.global.mbarrier::complete_tx::bytes [%0], [%1], %2, [%3];" :: "r"(dst), "l"(src), "r"(bytes), "r"(bar) : "memory");
}
__device__ __forceinline__ void bulk_store(void* dst, uint32_t src, uint32_t bytes) {
  asm volatile("cp.async.bulk.global.shared::cta.bulk_group [%0], [%1], %2;" :: "l"(dst), "r"(src), "r"(bytes) : "memory");
}
__device__ __forceinline__ void mbar_arrive(uint32_t bar) { asm volatile("mbarrier.arrive.shared::cta.b64 _, [%0];" :: "r"(bar) : "memory"); }
__device__ __forceinline__ void ldsm4t(uint32_t a, uint32_t& r0, uint32_t& r1, uint32_t& r2, uint32_t& r3) {
  asm volatile("ldmatrix.sync.aligned.m8n8.x4.trans.shared.b16 {%0,%1,%2,%3}, [%4];" : "=r"(r0), "=r"(r1), "=r"(r2), "=r"(r3) : "r"(a) : "memory");
}
__device__ __forceinline__ uint4 ld_pkt(const void* p) { uint4 v; asm volatile("ld.relaxed.gpu.global.v4.u32 {%0,%1,%2,%3}, [%4];" : "=r"(v.x), "=r"(v.y), "=r"(v.z), "=r"(v.w) : "l"(p) : "memory"); return v; }
__device__ __forceinline__ void st_pkt(void* p, uint32_t a, uint32_t b, uint32_t c, uint32_t d) { asm volatile("st.relaxed.gpu.global.v4.u32 [%0], {%1,%2,%3,%4};" :: "l"(p), "r"(a), "r"(b), "r"(c), "r"(d) : "memory"); }
__device__ __forceinline__ void spin_clks(uint32_t n) {
  asm volatile("{\n.reg .u32 a, c;\n.reg .pred p;\nmov.u32 a, %%clock;\nLAB_SPIN:\nmov.u32 c, %%clock;\nsub.u32 c, c, a;\nsetp.lt.u32 p, c, %0;\n@p nanosleep.u32 20;\n@p bra.uni LAB_SPIN;\n}" :: "r"(n) : "memory");
}
__device__ __forceinline__ uint32_t ldg32_rlx(const void* p) { uint32_t v; asm volatile("ld.relaxed.gpu.global.u32 %0, [%1];" : "=r"(v) : "l"(p) : "memory"); return v; }
__device__ __forceinline__ void publish(unsigned* cnt, int lane, uint32_t inc = 1) {
  asm volatile("{\n.reg .pred p;\nsetp.eq.b32 p, %2, 0;\n@p red.release.gpu.global.add.u32 [%0], %1;\n}" :: "l"(cnt), "r"(inc), "r"(lane) : "memory");
}
__device__ __forceinline__ void bulk_commit() { asm volatile("cp.async.bulk.commit_group;" ::: "memory"); }
__device__ __forceinline__ void bulk_wait0() { asm volatile("cp.async.bulk.wait_group 0;" ::: "memory"); }
__device__ __forceinline__ void bulk_wait0_read() { asm volatile("cp.async.bulk.wait_group.read 0;" ::: "memory"); }
__device__ __forceinline__ void l2_prefetch(const void* p) { asm volatile("prefetch.global.L2 [%0];" :: "l"(p) : "memory"); }
__device__ __forceinline__ uint32_t clk32() { uint32_t c; asm volatile("mov.u32 %0, %%clock;" : "=r"(c) :: "memory"); return c; }
__device__ __forceinline__ uint32_t gtime() { uint32_t t; asm volatile("mov.u32 %0, %%globaltimer_lo;" : "=r"(t) :: "memory"); return t; }
__device__ __forceinline__ void spin_until(uint32_t c0, uint32_t n) {
  asm volatile("{\n.reg .u32 c;\n.reg .pred p;\nLAB_SPIN:\nmov.u32 c, %%clock;\nsub.u32 c, c, %0;\nsetp.lt.s32 p, c, %1;\n@p bra.uni LAB_SPIN;\n}" :: "r"(c0), "r"(n) : "memory");
}
__device__ __forceinline__ void sleep_until(uint32_t c0, uint32_t n) {
  asm volatile("{\n.reg .u32 c;\n.reg .pred p;\nLAB_SPIN:\nmov.u32 c, %%clock;\nsub.u32 c, c, %0;\nsetp.lt.s32 p, c, %1;\n@p nanosleep.u32 20;\n@p bra.uni LAB_SPIN;\n}" :: "r"(c0), "r"(n) : "memory");
}
__device__ __forceinline__ uint32_t lds32(uint32_t a) { uint32_t v; asm volatile("ld.shared.u32 %0, [%1];" : "=r"(v) : "r"(a) : "memory"); return v; }
__device__ __forceinline__ void tmap_prefetch(const CUtensorMap* m) { asm volatile("prefetch.tensormap [%0];" :: "l"(m) : "memory"); }
__device__ __forceinline__ bool elect_one() { uint32_t el; asm volatile("{\n.reg .pred p;\nelect.sync _|p, 0xffffffff;\nselp.u32 %0, 1, 0, p;\n}" : "=r"(el)); return el; }
__device__ __forceinline__ void wg_fence() { asm volatile("wgmma.fence.sync.aligned;" ::: "memory"); }
__device__ __forceinline__ void wg_commit() { asm volatile("wgmma.commit_group.sync.aligned;" ::: "memory"); }
template <int N> __device__ __forceinline__ void wg_wait() { asm volatile("wgmma.wait_group.sync.aligned %0;" :: "n"(N) : "memory"); }
__device__ __forceinline__ uint64_t make_desc(uint32_t addr, uint32_t lbo, uint32_t sbo) {
  return (uint64_t)((addr & 0x3FFFF) >> 4) | ((uint64_t)(lbo >> 4) << 16) | ((uint64_t)(sbo >> 4) << 32) | (1ull << 62);
}
template <int ID, int N> __device__ __forceinline__ void bar_sync() { asm volatile("bar.sync %0, %1;" :: "n"(ID), "n"(N) : "memory"); }
template <int ID, int N> __device__ __forceinline__ void bar_arrive() { asm volatile("bar.arrive %0, %1;" :: "n"(ID), "n"(N) : "memory"); }
__device__ __forceinline__ void fence_async_global() { asm volatile("fence.acquire.gpu;\nfence.proxy.async.global;" ::: "memory"); }
__device__ __forceinline__ void fence_async_smem() { asm volatile("fence.proxy.async.shared::cta;" ::: "memory"); }
__device__ __forceinline__ void red_relaxed(unsigned* p, unsigned v) { asm volatile("red.relaxed.gpu.global.add.u32 [%0], %1;" :: "l"(p), "r"(v) : "memory"); }
__device__ __forceinline__ void wait_ge(const unsigned* p, unsigned target) {
  asm volatile("{\n.reg .pred p;\n.reg .u32 c, v;\nmov.u32 c, 0;\nLAB_WAIT:\n"
               "ld.relaxed.gpu.global.u32 v, [%0];\nsub.u32 v, v, %1;\nsetp.ge.s32 p, v, 0;\n@p bra LAB_DONE;\n"
               "add.u32 c, c, 1;\nsetp.lt.u32 p, c, 0x100000;\n@p bra LAB_WAIT;\ntrap;\nLAB_DONE:\n}" :: "l"(p), "r"(target) : "memory");
}
template <int GAP> __device__ __forceinline__ uint32_t wait_ge_time(const unsigned* p, unsigned target) {
  uint32_t t;
  asm volatile("{\n.reg .pred p;\n.reg .u32 c, v, a, h;\nmov.u32 c, 0;\nLAB_WAIT:\n"
               "ld.relaxed.gpu.global.v4.u32 {v, a, %0, h}, [%1];\nsub.u32 v, v, %2;\nsetp.ge.s32 p, v, 0;\nvote.sync.all.pred p, p, 0xffffffff;\n@p bra.uni LAB_DONE;\n"
               "mov.u32 a, %%clock;\nLAB_GAP:\nmov.u32 h, %%clock;\nsub.u32 h, h, a;\nsetp.lt.u32 p, h, %3;\n@p nanosleep.u32 20;\n@p bra.uni LAB_GAP;\n"
               "add.u32 c, c, 1;\nsetp.lt.u32 p, c, 0x100000;\n@p bra.uni LAB_WAIT;\ntrap;\nLAB_DONE:\n}" : "=r"(t) : "l"(p), "r"(target), "n"(GAP) : "memory");
  return t;
}
__device__ __forceinline__ uint32_t pack_bf16(float lo, float hi) { uint32_t r; asm("cvt.rn.bf16x2.f32 %0, %1, %2;" : "=r"(r) : "f"(hi), "f"(lo)); return r; }
__device__ __forceinline__ float bf_lo(uint32_t v) { return __uint_as_float(v << 16); }
__device__ __forceinline__ float bf_hi(uint32_t v) { return __uint_as_float(v & 0xffff0000u); }
__device__ __forceinline__ void stsm4(uint32_t a, uint32_t r0, uint32_t r1, uint32_t r2, uint32_t r3) {
  asm volatile("stmatrix.sync.aligned.m8n8.x4.shared.b16 [%0], {%1,%2,%3,%4};" :: "r"(a), "r"(r0), "r"(r1), "r"(r2), "r"(r3) : "memory");
}
__device__ __forceinline__ void stsm4t(uint32_t a, uint32_t r0, uint32_t r1, uint32_t r2, uint32_t r3) {
  asm volatile("stmatrix.sync.aligned.m8n8.x4.trans.shared.b16 [%0], {%1,%2,%3,%4};" :: "r"(a), "r"(r0), "r"(r1), "r"(r2), "r"(r3) : "memory");
}
__device__ __forceinline__ void sched_fence(uint32_t zero) {
  asm volatile("{\n.reg .pred p;\n.reg .u32 c;\nsetp.eq.b32 p, %0, 0;\n@p bra.uni LAB_D;\nLAB_F:\nnanosleep.u32 1;\nmov.u32 c, %%clock;\nsetp.lt.u32 p, c, %0;\n@p bra.uni LAB_F;\nLAB_D:\n}" :: "r"(zero) : "memory");
}
__device__ __forceinline__ uint32_t movm_t(uint32_t a) { uint32_t d; asm volatile("movmatrix.sync.aligned.m8n8.trans.b16 %0, %1;" : "=r"(d) : "r"(a)); return d; }
__device__ __forceinline__ uint4 lds128(uint32_t a) { uint4 v; asm volatile("ld.shared.v4.u32 {%0,%1,%2,%3}, [%4];" : "=r"(v.x), "=r"(v.y), "=r"(v.z), "=r"(v.w) : "r"(a) : "memory"); return v; }
__device__ __forceinline__ void sts128(uint32_t a, uint4 v) { asm volatile("st.shared.v4.u32 [%0], {%1,%2,%3,%4};" :: "r"(a), "r"(v.x), "r"(v.y), "r"(v.z), "r"(v.w) : "memory"); }
__device__ __forceinline__ void stg128(void* p, uint4 v) { asm volatile("st.global.v4.u32 [%0], {%1,%2,%3,%4};" :: "l"(p), "r"(v.x), "r"(v.y), "r"(v.z), "r"(v.w) : "memory"); }
__device__ __forceinline__ void mma16816z(float (&d)[4], uint32_t a0, uint32_t a1, uint32_t a2, uint32_t a3, uint32_t b0, uint32_t b1) {
  asm volatile("mma.sync.aligned.m16n8k16.row.col.f32.bf16.bf16.f32 {%0,%1,%2,%3}, {%4,%5,%6,%7}, {%8,%9}, {%10,%10,%10,%10};"
               : "=f"(d[0]), "=f"(d[1]), "=f"(d[2]), "=f"(d[3]) : "r"(a0), "r"(a1), "r"(a2), "r"(a3), "r"(b0), "r"(b1), "f"(0.f));
}
__device__ __forceinline__ void mma1688(float (&d)[4], uint32_t a0, uint32_t a1, uint32_t b0) {
  asm volatile("mma.sync.aligned.m16n8k8.row.col.f32.bf16.bf16.f32 {%0,%1,%2,%3}, {%4,%5}, {%6}, {%0,%1,%2,%3};"
               : "+f"(d[0]), "+f"(d[1]), "+f"(d[2]), "+f"(d[3]) : "r"(a0), "r"(a1), "r"(b0));
}
__device__ __forceinline__ float ex2(float x) { float y; asm("ex2.approx.ftz.f32 %0, %1;" : "=f"(y) : "f"(x)); return y; }
__device__ __forceinline__ float rcp(float x) { float y; asm("rcp.approx.ftz.f32 %0, %1;" : "=f"(y) : "f"(x)); return y; }
__device__ __forceinline__ float gelu_arg(float x) { return x * fmaf(0.0356774081363001f, x * x, 0.7978845608028654f); }
__device__ __forceinline__ float tanh_fast(float z) { float t; asm volatile("tanh.approx.f32 %0, %1;" : "=f"(t) : "f"(z)); return t; }
__device__ __forceinline__ float gelu2(float x) { return fmaf(x, tanh_fast(gelu_arg(x)), x); }
__device__ __forceinline__ float pin(float x) { asm volatile("" : "+f"(x)); return x; }

__device__ __forceinline__ void wgmma_n192_ta0_tb1(float (&d)[96], uint64_t da, uint64_t db, int scale_d) {
  asm volatile("{\n.reg .pred p;\nsetp.ne.b32 p, %98, 0;\n"
    "wgmma.mma_async.sync.aligned.m64n192k16.f32.bf16.bf16 "
    "{%0,%1,%2,%3,%4,%5,%6,%7,%8,%9,%10,%11,%12,%13,%14,%15,%16,%17,%18,%19,%20,%21,%22,%23,%24,%25,%26,%27,%28,%29,%30,%31,%32,%33,%34,%35,%36,%37,%38,%39,%40,%41,%42,%43,%44,%45,%46,%47,%48,%49,%50,%51,%52,%53,%54,%55,%56,%57,%58,%59,%60,%61,%62,%63,%64,%65,%66,%67,%68,%69,%70,%71,%72,%73,%74,%75,%76,%77,%78,%79,%80,%81,%82,%83,%84,%85,%86,%87,%88,%89,%90,%91,%92,%93,%94,%95}, "
    "%96, %97, p, 1, 1, 0, 1;\n}\n"
    :
      "+f"(d[0]), "+f"(d[1]), "+f"(d[2]), "+f"(d[3]), "+f"(d[4]), "+f"(d[5]), "+f"(d[6]), "+f"(d[7]), "+f"(d[8]), "+f"(d[9]),
      "+f"(d[10]), "+f"(d[11]), "+f"(d[12]), "+f"(d[13]), "+f"(d[14]), "+f"(d[15]), "+f"(d[16]), "+f"(d[17]), "+f"(d[18]), "+f"(d[19]),
      "+f"(d[20]), "+f"(d[21]), "+f"(d[22]), "+f"(d[23]), "+f"(d[24]), "+f"(d[25]), "+f"(d[26]), "+f"(d[27]), "+f"(d[28]), "+f"(d[29]),
      "+f"(d[30]), "+f"(d[31]), "+f"(d[32]), "+f"(d[33]), "+f"(d[34]), "+f"(d[35]), "+f"(d[36]), "+f"(d[37]), "+f"(d[38]), "+f"(d[39]),
      "+f"(d[40]), "+f"(d[41]), "+f"(d[42]), "+f"(d[43]), "+f"(d[44]), "+f"(d[45]), "+f"(d[46]), "+f"(d[47]), "+f"(d[48]), "+f"(d[49]),
      "+f"(d[50]), "+f"(d[51]), "+f"(d[52]), "+f"(d[53]), "+f"(d[54]), "+f"(d[55]), "+f"(d[56]), "+f"(d[57]), "+f"(d[58]), "+f"(d[59]),
      "+f"(d[60]), "+f"(d[61]), "+f"(d[62]), "+f"(d[63]), "+f"(d[64]), "+f"(d[65]), "+f"(d[66]), "+f"(d[67]), "+f"(d[68]), "+f"(d[69]),
      "+f"(d[70]), "+f"(d[71]), "+f"(d[72]), "+f"(d[73]), "+f"(d[74]), "+f"(d[75]), "+f"(d[76]), "+f"(d[77]), "+f"(d[78]), "+f"(d[79]),
      "+f"(d[80]), "+f"(d[81]), "+f"(d[82]), "+f"(d[83]), "+f"(d[84]), "+f"(d[85]), "+f"(d[86]), "+f"(d[87]), "+f"(d[88]), "+f"(d[89]),
      "+f"(d[90]), "+f"(d[91]), "+f"(d[92]), "+f"(d[93]), "+f"(d[94]), "+f"(d[95])
    : "l"(da), "l"(db), "r"(scale_d));
}

__device__ __forceinline__ void wgmma_n48_ta0_tb1(float (&d)[24], uint64_t da, uint64_t db, int scale_d) {
  asm volatile("{\n.reg .pred p;\nsetp.ne.b32 p, %26, 0;\n"
    "wgmma.mma_async.sync.aligned.m64n48k16.f32.bf16.bf16 "
    "{%0,%1,%2,%3,%4,%5,%6,%7,%8,%9,%10,%11,%12,%13,%14,%15,%16,%17,%18,%19,%20,%21,%22,%23}, "
    "%24, %25, p, 1, 1, 0, 1;\n}\n"
    :
      "+f"(d[0]), "+f"(d[1]), "+f"(d[2]), "+f"(d[3]), "+f"(d[4]), "+f"(d[5]), "+f"(d[6]), "+f"(d[7]), "+f"(d[8]), "+f"(d[9]),
      "+f"(d[10]), "+f"(d[11]), "+f"(d[12]), "+f"(d[13]), "+f"(d[14]), "+f"(d[15]), "+f"(d[16]), "+f"(d[17]), "+f"(d[18]), "+f"(d[19]),
      "+f"(d[20]), "+f"(d[21]), "+f"(d[22]), "+f"(d[23])
    : "l"(da), "l"(db), "r"(scale_d));
}

__device__ __forceinline__ void wgmma_n128_ta1_tb1(float (&d)[64], uint64_t da, uint64_t db, int scale_d) {
  asm volatile("{\n.reg .pred p;\nsetp.ne.b32 p, %66, 0;\n"
    "wgmma.mma_async.sync.aligned.m64n128k16.f32.bf16.bf16 "
    "{%0,%1,%2,%3,%4,%5,%6,%7,%8,%9,%10,%11,%12,%13,%14,%15,%16,%17,%18,%19,%20,%21,%22,%23,%24,%25,%26,%27,%28,%29,%30,%31,%32,%33,%34,%35,%36,%37,%38,%39,%40,%41,%42,%43,%44,%45,%46,%47,%48,%49,%50,%51,%52,%53,%54,%55,%56,%57,%58,%59,%60,%61,%62,%63}, "
    "%64, %65, p, 1, 1, 1, 1;\n}\n"
    :
      "+f"(d[0]), "+f"(d[1]), "+f"(d[2]), "+f"(d[3]), "+f"(d[4]), "+f"(d[5]), "+f"(d[6]), "+f"(d[7]), "+f"(d[8]), "+f"(d[9]),
      "+f"(d[10]), "+f"(d[11]), "+f"(d[12]), "+f"(d[13]), "+f"(d[14]), "+f"(d[15]), "+f"(d[16]), "+f"(d[17]), "+f"(d[18]), "+f"(d[19]),
      "+f"(d[20]), "+f"(d[21]), "+f"(d[22]), "+f"(d[23]), "+f"(d[24]), "+f"(d[25]), "+f"(d[26]), "+f"(d[27]), "+f"(d[28]), "+f"(d[29]),
      "+f"(d[30]), "+f"(d[31]), "+f"(d[32]), "+f"(d[33]), "+f"(d[34]), "+f"(d[35]), "+f"(d[36]), "+f"(d[37]), "+f"(d[38]), "+f"(d[39]),
      "+f"(d[40]), "+f"(d[41]), "+f"(d[42]), "+f"(d[43]), "+f"(d[44]), "+f"(d[45]), "+f"(d[46]), "+f"(d[47]), "+f"(d[48]), "+f"(d[49]),
      "+f"(d[50]), "+f"(d[51]), "+f"(d[52]), "+f"(d[53]), "+f"(d[54]), "+f"(d[55]), "+f"(d[56]), "+f"(d[57]), "+f"(d[58]), "+f"(d[59]),
      "+f"(d[60]), "+f"(d[61]), "+f"(d[62]), "+f"(d[63])
    : "l"(da), "l"(db), "r"(scale_d));
}

__device__ __forceinline__ void wgmma_n80_ta0_tb0(float (&d)[40], uint64_t da, uint64_t db, int scale_d) {
  asm volatile("{\n.reg .pred p;\nsetp.ne.b32 p, %42, 0;\n"
    "wgmma.mma_async.sync.aligned.m64n80k16.f32.bf16.bf16 "
    "{%0,%1,%2,%3,%4,%5,%6,%7,%8,%9,%10,%11,%12,%13,%14,%15,%16,%17,%18,%19,%20,%21,%22,%23,%24,%25,%26,%27,%28,%29,%30,%31,%32,%33,%34,%35,%36,%37,%38,%39}, "
    "%40, %41, p, 1, 1, 0, 0;\n}\n"
    :
      "+f"(d[0]), "+f"(d[1]), "+f"(d[2]), "+f"(d[3]), "+f"(d[4]), "+f"(d[5]), "+f"(d[6]), "+f"(d[7]), "+f"(d[8]), "+f"(d[9]),
      "+f"(d[10]), "+f"(d[11]), "+f"(d[12]), "+f"(d[13]), "+f"(d[14]), "+f"(d[15]), "+f"(d[16]), "+f"(d[17]), "+f"(d[18]), "+f"(d[19]),
      "+f"(d[20]), "+f"(d[21]), "+f"(d[22]), "+f"(d[23]), "+f"(d[24]), "+f"(d[25]), "+f"(d[26]), "+f"(d[27]), "+f"(d[28]), "+f"(d[29]),
      "+f"(d[30]), "+f"(d[31]), "+f"(d[32]), "+f"(d[33]), "+f"(d[34]), "+f"(d[35]), "+f"(d[36]), "+f"(d[37]), "+f"(d[38]), "+f"(d[39])
    : "l"(da), "l"(db), "r"(scale_d));
}

__device__ __forceinline__ void wgmma_n80_ta1_tb0(float (&d)[40], uint64_t da, uint64_t db, int scale_d) {
  asm volatile("{\n.reg .pred p;\nsetp.ne.b32 p, %42, 0;\n"
    "wgmma.mma_async.sync.aligned.m64n80k16.f32.bf16.bf16 "
    "{%0,%1,%2,%3,%4,%5,%6,%7,%8,%9,%10,%11,%12,%13,%14,%15,%16,%17,%18,%19,%20,%21,%22,%23,%24,%25,%26,%27,%28,%29,%30,%31,%32,%33,%34,%35,%36,%37,%38,%39}, "
    "%40, %41, p, 1, 1, 1, 0;\n}\n"
    :
      "+f"(d[0]), "+f"(d[1]), "+f"(d[2]), "+f"(d[3]), "+f"(d[4]), "+f"(d[5]), "+f"(d[6]), "+f"(d[7]), "+f"(d[8]), "+f"(d[9]),
      "+f"(d[10]), "+f"(d[11]), "+f"(d[12]), "+f"(d[13]), "+f"(d[14]), "+f"(d[15]), "+f"(d[16]), "+f"(d[17]), "+f"(d[18]), "+f"(d[19]),
      "+f"(d[20]), "+f"(d[21]), "+f"(d[22]), "+f"(d[23]), "+f"(d[24]), "+f"(d[25]), "+f"(d[26]), "+f"(d[27]), "+f"(d[28]), "+f"(d[29]),
      "+f"(d[30]), "+f"(d[31]), "+f"(d[32]), "+f"(d[33]), "+f"(d[34]), "+f"(d[35]), "+f"(d[36]), "+f"(d[37]), "+f"(d[38]), "+f"(d[39])
    : "l"(da), "l"(db), "r"(scale_d));
}

__device__ __forceinline__ void wgmma_n80_ta0_tb1(float (&d)[40], uint64_t da, uint64_t db, int scale_d) {
  asm volatile("{\n.reg .pred p;\nsetp.ne.b32 p, %42, 0;\n"
    "wgmma.mma_async.sync.aligned.m64n80k16.f32.bf16.bf16 "
    "{%0,%1,%2,%3,%4,%5,%6,%7,%8,%9,%10,%11,%12,%13,%14,%15,%16,%17,%18,%19,%20,%21,%22,%23,%24,%25,%26,%27,%28,%29,%30,%31,%32,%33,%34,%35,%36,%37,%38,%39}, "
    "%40, %41, p, 1, 1, 0, 1;\n}\n"
    :
      "+f"(d[0]), "+f"(d[1]), "+f"(d[2]), "+f"(d[3]), "+f"(d[4]), "+f"(d[5]), "+f"(d[6]), "+f"(d[7]), "+f"(d[8]), "+f"(d[9]),
      "+f"(d[10]), "+f"(d[11]), "+f"(d[12]), "+f"(d[13]), "+f"(d[14]), "+f"(d[15]), "+f"(d[16]), "+f"(d[17]), "+f"(d[18]), "+f"(d[19]),
      "+f"(d[20]), "+f"(d[21]), "+f"(d[22]), "+f"(d[23]), "+f"(d[24]), "+f"(d[25]), "+f"(d[26]), "+f"(d[27]), "+f"(d[28]), "+f"(d[29]),
      "+f"(d[30]), "+f"(d[31]), "+f"(d[32]), "+f"(d[33]), "+f"(d[34]), "+f"(d[35]), "+f"(d[36]), "+f"(d[37]), "+f"(d[38]), "+f"(d[39])
    : "l"(da), "l"(db), "r"(scale_d));
}

template <bool ODD>
__device__ __forceinline__ void pack_qkv(const float (&acc)[96], const float (&acct)[24], uint32_t (&q)[10][2], uint32_t (&k)[3][10], uint32_t (&v)[3][10]) {
#define SRC(sec, g) (ODD ? ((g) < 2 ? &acct[8 * (sec) + 4 * (g)] : &acc[32 * (sec) + 4 * ((g) - 2)]) \
                         : ((g) < 8 ? &acc[32 * (sec) + 4 * (g)] : &acct[8 * (sec) + 4 * ((g) - 8)]))
#pragma unroll
  for (int g = 0; g < 10; g++) {
    q[g][0] = pack_bf16(SRC(0, g)[0], SRC(0, g)[1]); q[g][1] = pack_bf16(SRC(0, g)[2], SRC(0, g)[3]);
    k[1][g] = pack_bf16(SRC(1, g)[0], SRC(1, g)[1]); k[2][g] = pack_bf16(SRC(1, g)[2], SRC(1, g)[3]);
    v[1][g] = pack_bf16(SRC(2, g)[0], SRC(2, g)[1]); v[2][g] = pack_bf16(SRC(2, g)[2], SRC(2, g)[3]);
  }
#undef SRC
}

__device__ __forceinline__ uint32_t fresh(uint32_t x, uint32_t zero) { uint32_t r; asm volatile("xor.b32 %0, %1, %2;" : "=r"(r) : "r"(x), "r"(zero)); return r; }
__device__ __forceinline__ void attention(const uint32_t (&q)[10][2], const uint32_t (&k)[3][10], const uint32_t (&v)[3][10], bool first, int lane,
                                          uint32_t zero, uint32_t gate, uint32_t stg) {
  const int r = lane >> 2, qd = lane & 3;
  const bool lo = qd < 2, c0cur = 2 * qd <= r, c1cur = 2 * qd + 1 <= r;
  const uint32_t mcur = fresh((c0cur ? 0xffffu : 0u) | (c1cur ? 0xffff0000u : 0u), zero);
  const float sc = 0.22360679774997896f * 1.4426950408889634f;
  const float ninf = __int_as_float(0xff800000);
  uint32_t qm[4][2], an[2][4][4], as[2][2][4], kp[4][2];
#pragma unroll
  for (int h = 0; h < 4; h++) {
    const bool keep = (h & 1) ? !lo : lo;
    const int g0 = 5 * (h >> 1) + ((h & 1) ? 3 : 0), gs = 5 * (h >> 1) + 2;
    qm[h][0] = fresh(keep ? q[gs][0] : 0u, zero); qm[h][1] = fresh(keep ? q[gs][1] : 0u, zero);
    kp[h][0] = fresh(k[0][g0], zero); kp[h][1] = fresh(k[0][g0 + 1], zero);
#pragma unroll
    for (int hf = 0; hf < 2; hf++) {
      an[hf][h][0] = fresh(v[2 * hf][g0], zero); an[hf][h][1] = fresh(v[2 * hf][g0 + 1], zero);
      an[hf][h][2] = fresh(v[1][g0], zero); an[hf][h][3] = fresh(v[1][g0 + 1], zero);
      if (!(h & 1)) {
        as[hf][h >> 1][0] = fresh(v[2 * hf][gs], zero); as[hf][h >> 1][1] = fresh(0x3f803f80u, zero);
        as[hf][h >> 1][2] = fresh(v[1][gs], zero); as[hf][h >> 1][3] = fresh(0x3f803f80u, zero);
      }
    }
  }
  mbar_wait(gate, 0);
  float l0[2][4], l1[2][4], m[2][4];
#pragma unroll
  for (int h = 0; h < 4; h++) {
    const int g0 = 5 * (h >> 1) + ((h & 1) ? 3 : 0), gs = 5 * (h >> 1) + 2;
    float s[3][4];
#pragma unroll
    for (int n = 0; n < 3; n++) mma16816z(s[n], q[g0][0], q[g0][1], q[g0 + 1][0], q[g0 + 1][1], n ? k[n][g0] : kp[h][0], n ? k[n][g0 + 1] : kp[h][1]);
#pragma unroll
    for (int n = 0; n < 3; n++) mma1688(s[n], qm[h][0], qm[h][1], k[n][gs]);
    l0[0][h] = c0cur ? s[1][0] : (first ? ninf : s[0][0]); l1[0][h] = c1cur ? s[1][1] : (first ? ninf : s[0][1]);
    l0[1][h] = c0cur ? s[2][2] : s[1][2];                  l1[1][h] = c1cur ? s[2][3] : s[1][3];
  }
#pragma unroll
  for (int h = 0; h < 4; h++)
#pragma unroll
    for (int hf = 0; hf < 2; hf++) { m[hf][h] = fmaxf(l0[hf][h], l1[hf][h]); m[hf][h] = fmaxf(m[hf][h], __shfl_xor_sync(~0u, m[hf][h], 1)); }
#pragma unroll
  for (int h = 0; h < 4; h++)
#pragma unroll
    for (int hf = 0; hf < 2; hf++) m[hf][h] = fmaxf(m[hf][h], __shfl_xor_sync(~0u, m[hf][h], 2)) * -sc;
  float on[2][4][4], os[2][4][4];
#pragma unroll
  for (int h = 0; h < 4; h++)
#pragma unroll
    for (int hf = 0; hf < 2; hf++) {
      const uint32_t p = pack_bf16(ex2(fmaf(l0[hf][h], sc, m[hf][h])), ex2(fmaf(l1[hf][h], sc, m[hf][h])));
      const uint32_t pe = hf ? p & mcur : p & ~mcur, pm = hf ? p & ~mcur : p & mcur;
      mma16816z(os[hf][h], as[hf][h >> 1][0], as[hf][h >> 1][1], as[hf][h >> 1][2], as[hf][h >> 1][3], pe, pm);
      mma16816z(on[hf][h], an[hf][h][0], an[hf][h][1], an[hf][h][2], an[hf][h][3], pe, pm);
    }
  uint32_t sh[2][2];
#pragma unroll
  for (int h = 0; h < 4; h++) {
    const int g0 = 5 * (h >> 1) + ((h & 1) ? 3 : 0);
    uint32_t og[2][2];
#pragma unroll
    for (int hf = 0; hf < 2; hf++) {
      const float rr = rcp(os[hf][h][2] * os[hf][h][3]), r0 = rr * os[hf][h][3], r1 = rr * os[hf][h][2];
      og[0][hf] = pack_bf16(on[hf][h][0] * r0, on[hf][h][1] * r1);
      og[1][hf] = pack_bf16(on[hf][h][2] * r0, on[hf][h][3] * r1);
      const uint32_t t = pack_bf16(os[hf][h][0] * r0, os[hf][h][1] * r1);
      sh[h >> 1][hf] = ((h & 1) && r < 4) ? sh[h >> 1][hf] : t;
    }
    stsm4t(stg + g0 * 2048, og[0][0], og[0][1], og[1][0], og[1][1]);
    if (ATF && h < 3) sched_fence(zero);
  }
  stsm4t(stg + 2 * 2048 + (lane >> 4) * (4 * 2048), sh[0][0], sh[0][1], sh[1][0], sh[1][1]);
}

__device__ __forceinline__ int cta_id() { int b; asm volatile("mov.u32 %0, %%ctaid.x;" : "=r"(b)); return b; }
__device__ __forceinline__ int tile_m(int b) { const int U = b >> 3; return ((U >> 3) ? 7 - (U & 7) : (U & 7)) * 2 + ((b & 7) >> 2); }
__device__ __forceinline__ int tile_n(int b) { return (b >> 6) * 4 + (b & 3); }
__device__ __forceinline__ int tile_d(int b) { const int u = (b >> 1) - 4, c = u / 10, r = u - c * 10; return (c & 1) ? 9 - r : r; }
__device__ __forceinline__ int tile_f(int b) { return (((b >> 1) - 4) / 10) * 2 + (b & 1); }
__device__ __forceinline__ int w_main(int hg) { return hg * 80 + (hg & 1) * 16; }
__device__ __forceinline__ int w_tail(int hg) { return hg * 80 + ((hg & 1) ? 0 : 64); }

__device__ __forceinline__ bool is_light(int b) { return ((b + 1) & 2) == 0; }
__device__ __forceinline__ void g1_loads(const Maps& maps, uint32_t dst, int kb, int mt, int wmain, int wtail, uint32_t bar0, uint32_t bar1) {
  tma3(dst + 16384, &maps.wa, wmain, kb * 64, 0, bar0);
  tma3(dst, &maps.x, kb * 64, mt * 64, 0, bar0);
  tma3(dst + 16384 + 24576, &maps.wb, wtail, kb * 64, 0, bar0);
  tma3(dst + 16384 + 12288, &maps.wa, wmain, kb * 64 + 32, 0, bar1);
  tma3(dst + 16384 + 24576 + 3072, &maps.wb, wtail, kb * 64 + 32, 0, bar1);
}

__global__ void __launch_bounds__(NTHREADS, 1)
fused_kernel(Scratch* __restrict__ scr, const __nv_bfloat16* __restrict__ x,
             const __nv_bfloat16* __restrict__ w1, const __nv_bfloat16* __restrict__ b1,
             const __nv_bfloat16* __restrict__ b2, const __nv_bfloat16* __restrict__ gate_w, uint32_t zero, const __grid_constant__ Maps maps) {
  extern __shared__ __align__(1024) uint8_t smem_raw[];
  uint32_t sb; asm volatile("mov.u32 %0, %1;" : "=r"(sb) : "r"((uint32_t)__cvta_generic_to_shared(smem_raw)));
  const uint32_t full1 = sb + BAR_OFF, empty1 = full1 + 32, full2 = full1 + 64, empty2 = full1 + 128, full3 = full1 + 192, empty3 = full1 + 256,
                 go = full1 + 320, prepl = full1 + 328, wod = full1 + 344, epb = full1 + 352, prog = full1 + 360, flh = full1 + 368, flo = full1 + 376,
                 flu = full1 + 384, upub = full1 + 400, gate = full1 + 408, xchd = full1 + 416, prepd = full1 + 424, xrd = full1 + 432,  eps = full1 + 448, half0 = full1 + 480, bown = full3 + 56, ownd = empty3 + 56;
  const uint32_t cstart = clk32();
  const int tid = threadIdx.x, lane = tid & 31;
  const int warp = __shfl_sync(~0u, tid >> 5, 0);

  if (warp == 12) {
    const bool el = elect_one();
    if (el) {
      mbar_init(half0, 1); mbar_init(full1 + 16, 1);
      asm volatile("fence.mbarrier_init.release.cluster;" ::: "memory");
    }
    __syncwarp();
    bar_arrive<14, 512>();
    if (elect_one()) {
      const int b = cta_id(), mt = tile_m(b), wmain = w_main(tile_n(b)), wtail = w_tail(tile_n(b));
      mbar_expect_tx(full1 + 16, 15360);
      mbar_expect_tx(half0, 16384 + 15360);
      g1_loads(maps, sb + 2 * G1_STAGE, 0, mt, wmain, wtail, half0, full1 + 16);
    }
    __syncwarp();
    bar_sync<15, 512>();
  } else if (warp < 15) {
    const int w = warp > 12 ? warp - 1 : warp;
    if (elect_one()) {
      const int c = w == 1 || w == 8 || w == 9 ? 2 : 1;
      mbar_init(full1 + 32 * w, w == 13 ? 8 : c);
      mbar_init(full1 + 32 * w + 8, w == 13 ? 4 : c);
      if (w) mbar_init(full1 + 32 * w + 16, w == 13 ? 4 : c);
      mbar_init(full1 + 32 * w + 24, w == 13 ? 8 : w == 10 || w == 12 ? 4 : c);
      asm volatile("fence.mbarrier_init.release.cluster;" ::: "memory");
    }
    __syncwarp();
  } else {
    asm volatile("st.shared.u32 [%0], %1;" :: "r"(eps + 16), "r"(zero & (uint32_t)(size_t)scr) : "memory");
    if (sb & 1023) asm volatile("trap;");
  }
  if (warp != 12) { bar_arrive<15, 512>(); bar_sync<14, 512>(); }

  if (warp >= 12) {
    asm volatile("setmaxnreg.dec.sync.aligned.u32 40;");
    if (warp == 12) {
      if (elect_one()) {
        const int b = cta_id();
        const bool has_g2 = b >= 8;
        {
        const int mt = tile_m(b), wmain = w_main(tile_n(b)), wtail = w_tail(tile_n(b));
#pragma unroll 1
        for (int kb = 2; kb < 10; kb++) {
          const int st = (kb + 2) & 3;
          if (kb >= 4) mbar_wait(empty1 + 8 * st, ((kb >> 2) - 1) & 1);
          else if (kb > 0) spin_until(cstart, kb == 2 ? G1D2 : G1D3);
          uint64_t tnow; asm volatile("mov.u64 %0, %%globaltimer;" : "=l"(tnow) :: "memory");
          const uint32_t bar = full1 + 8 * st, dst = sb + st * G1_STAGE;

          mbar_expect_tx(bar, G1_STAGE);
          g1_loads(maps, dst, kb, mt, wmain, wtail, bar, bar);
          if (kb == SYNC_KB + 4) {
            mbar_wait(epb, 0);
            asm volatile("red.relaxed.gpu.global.max.u64 [%0], %1;" :: "l"(&scr->sync[162]), "l"(tnow) : "memory");
            red_relaxed(&scr->sync[160], 1);
            mbar_arrive(prog);
            PROF_T(19);
          }
          if (kb == PREP_KB) {
            mbar_expect_tx(prepl, 8 * D_ * 2 + D_ * 2);
            bulk_load(sb + XROW_OFF, x + (size_t)b * 8 * D_, 8 * D_ * 2, prepl);
            bulk_load(sb + GW_OFF, gate_w, D_ * 2, prepl);
          }
          if (kb == PREP2_KB) {
            mbar_expect_tx(prepl + 8, 8 * D_ * 2);
            bulk_load(sb + XROW_OFF + 8 * D_ * 2, x + (size_t)(S_ / 2 + b * 8) * D_, 8 * D_ * 2, prepl + 8);
          }
        }
        }
        if (has_g2) {
          const int b2_ = cta_id(), dt = tile_d(b2_), ft = tile_f(b2_);
          tmap_prefetch(&maps.h); tmap_prefetch(&maps.w1);
          mbar_wait(go, 0);
          uint32_t c0 = lds32(eps + 12);
#pragma unroll 1
          for (int r = 0; r < 4; r++) {
            if (r == 2) mbar_wait(flh, 1);
#pragma unroll
            for (int i = 0; i < 8; i++) {
              const uint32_t first = i == 0 ? xrd : i == 7 ? prepd : empty1 + 8 * (i >> 1);
              mbar_wait(r ? empty2 + 8 * i : first, r ? (r - 1) & 1 : (i > 0 && i < 4 ? 1 : 0));
              if (i == 4 && r == 0) c0 += FILL4 - 4 * G2P;
              if (i == 6 && r == 0) c0 += FILL6 - FILL4 - 2 * G2P;
              if (r < SCHED_R) spin_until(c0, i * G2P);
              mbar_expect_tx(full2 + 8 * i, G2_SLOT);
              tma3(sb + g2_slot(i) + 8192, &maps.w1, 0, r * 512 + i * 64, ft * 2, full2 + 8 * i);
              if (i > HI || r) tma2(sb + g2_slot(i), &maps.h, dt * 64, r * 512 + i * 64, full2 + 8 * i);
              else if (i == HI) {
                mbar_wait(flh, 0);
#pragma unroll 1
                for (int j = 0; j <= HI; j++) tma2(sb + g2_slot(j), &maps.h, dt * 64, j * 64, full2 + 8 * j);
              }
            }
            c0 += 8 * G2P;
          }
        } else {
          mbar_wait(empty1 + 8 * 3, 0);
          const int nt_ = (107 - b) >> 3;
          mbar_expect_tx(full2, nt_ * 8192);
#pragma unroll 1
          for (int j = 0; j < nt_; j++) {
            const int t = b + 8 * j, kt = t / 10;
            tma3(sb + j * 8192, &maps.wo, (t - kt * 10) * 64, (kt >> 1) * 16, (kt & 1) * 4, full2);
            spin_clks(80);
          }
          mbar_wait(wod, 0);
        }
        tmap_prefetch(&maps.w2); tmap_prefetch(&maps.bc); tmap_prefetch(&maps.ust); tmap_prefetch(&maps.woa); tmap_prefetch(&maps.wob);
        PROF_T(9);
        const int b3_ = cta_id(), pm = tile_m(b3_), pn = tile_n(b3_);
#pragma unroll 1
        for (int i = 0; i < P2N - 1; i++) {
          if (has_g2) mbar_wait(empty2 + 8 * (i + 1), 1);
          mbar_expect_tx(full3 + 8 * i, P2_SLOT);
          tma3(sb + i * P2_SLOT, &maps.w2, 0, i * 128, pm * 2, full3 + 8 * i);
        }
        if (has_g2) mbar_wait(empty2 + 8 * 7, 1);
        mbar_expect_tx(bown, 12800);
        tma2(sb + (P2N - 1) * P2_SLOT, &maps.woa, pn * 80, pn * 80, bown);
        tma2(sb + (P2N - 1) * P2_SLOT + 10240, &maps.wob, pn * 80 + 64, pn * 80, bown);
        PROF_T(11);
        if (has_g2) mbar_wait(upub, 0); else { mbar_wait(go, 0); sleep_until(lds32(eps + 12), IDLE_CLK); }
        wait_ge(&scr->sync[96], lds32(eps + 4)); fence_async_global();
        PROF_T(12);
#pragma unroll 1
        for (int i = 0; i < P2N; i++) {
          if (i == P2N - 1) {
            mbar_wait(ownd, 0);
            mbar_expect_tx(full3 + 8 * i, P2_SLOT);
            tma3(sb + i * P2_SLOT, &maps.w2, 0, i * 128, pm * 2, full3 + 8 * i);
          }
          tma3(sb + i * P2_SLOT + 16384, &maps.bc, 0, pn * 10, 80 + i * 16, full3 + 8 * i);
          if (i == 0) mbar_arrive(flu);
        }
        int i = 0, ph = 0;
#pragma unroll 1
        for (int kb = P2N; kb < 34; kb++) {
          mbar_wait(empty3 + 8 * i, ph);
          const uint32_t bar = full3 + 8 * i, dst = sb + i * P2_SLOT;
          mbar_expect_tx(bar, P2_SLOT);
          int kc;
          if (kb < 24) {
            const int f0 = kb < 12 ? kb * 128 : (kb - 12) * 128 + 64;
            tma3(dst, &maps.w2, 0, f0, pm * 2, bar);
            kc = D_ + f0;
            if (kb == 12) mbar_wait(flu + 8, 0);
          } else {
            if (kb == 24) { PROF_T(10); mbar_wait(flo, 0); }
            const int k3 = (kb - 24) ^ 1 ^ (pn >> 2);
            bulk_load(dst, scr->o + (size_t)(pm * 80 + k3 * 8) * 1024, 16384, bar);
            kc = k3 * 64;
          }
          tma3(dst + 16384, &maps.bc, 0, pn * 10, kc >> 3, bar);
          if (++i == P2N) { i = 0; ph ^= 1; }
        }
        tmap_prefetch(&maps.outa); tmap_prefetch(&maps.outb);
      }
    } else if (warp < 15) {
            const int rr = warp - 13, b = cta_id(), mt = tile_m(b), hg = tile_n(b);
      const bool has_g2 = b >= 8;
      const uint32_t c0 = cstart;
      if (rr == 0) {
        if (elect_one()) {
          const int wmain = w_main(hg), wtail = w_tail(hg);
          mbar_expect_tx(full1 + 24, G1_STAGE);
          spin_until(cstart, G1D);
          g1_loads(maps, sb + 3 * G1_STAGE, 1, mt, wmain, wtail, full1 + 24, full1 + 24);
        }
        __syncwarp();
      }
      if (rr == 1) {
        const bool light = is_light(b);
#pragma unroll 1
        for (int i = W10; i < W1A; i++) {
          sleep_until(c0, PF1_0 + i * PF1_P);
          if (light) l2_prefetch((const char*)w1 + (size_t)(i * NCTA + b) * 4096 + lane * 128);
          if (light) l2_prefetch((const char*)w1 + (size_t)(i * NCTA + (b ^ 1)) * 4096 + lane * 128);
        }
      }
      mbar_wait(epb, 0);
      {
        if (rr == 0) bar_sync<9, 160>(); else bar_sync<10, 160>();
        publish(&scr->sync[rr * 32], lane);
        PROF_W(13 + 17 * rr, lane == 0);
      }
      if (rr == 1) {
#pragma unroll 1
        for (int i = W1A; i < W1E; i++) { sleep_until(c0, PF1_0 + i * PF1_P); l2_prefetch((const char*)w1 + (size_t)(i * NCTA + b) * 4096 + lane * 128); }
      }
      if (has_g2) {
        const int dt = tile_d(b), ft = tile_f(b);
        if (rr == 0) bar_sync<6, 160>();
        else {
          bar_sync<7, 160>();
          mbar_wait(U1W ? flu : upub, 0);
          if (U1D) spin_clks(U1D);
          if (elect_one()) { tma_store3(&maps.ust, sb + XCH_OFF, 0, dt * 8, 88 + ft * 16); bulk_commit(); bulk_wait0(); }
          __syncwarp();
        }
        publish(&scr->sync[96 + 32 * rr], lane);
        mbar_arrive_if(upub, rr == 0 && lane == 0);
        PROF_W(5 + 17 * rr, lane == 0);
      }
      if (rr == 0) {
        char* op = (char*)scr->o + (size_t)(mt * 40 + hg) * 4096;
        bar_sync<4, 288>();
        mbar_wait(prepd, 0);
        mbar_wait(flu + 8 * OAFT, 0);
        if (elect_one()) {
          const uint32_t cs = clk32();
#pragma unroll 1
          for (int i = 0; i < 5; i++) {
            sleep_until(cs, ODELAY + i * PACE);
            bulk_store(op + i * 32768, sb + OSTG_OFF + i * 4096, 4096);
          }
          bulk_store(scr->gate + b * 32, sb + GV_OFF, 128);
          bulk_store(scr->gate + (NCTA + b) * 32, sb + GV_OFF + 32, 128);
          bulk_commit(); bulk_wait0();
          PROF_T(29);
        }
        __syncwarp();
        publish(&scr->sync[64], lane);
        PROF_W(14, lane == 0);
      }
    } else {
      const int b = cta_id();
      const unsigned per = lane == 2 ? 2 * NCTA : NCTA;
      const unsigned tg = (ldg32_rlx(&scr->sync[(lane < 6 ? lane : 0) * 32]) & ~(per - 1)) + per;
      const unsigned t0 = __shfl_sync(~0u, tg, 0), t1 = __shfl_sync(~0u, tg, 1), t2 = __shfl_sync(~0u, tg, 2), t3 = __shfl_sync(~0u, tg, 3), t4 = __shfl_sync(~0u, tg, 4), t5 = __shfl_sync(~0u, tg, 5);
      if (elect_one()) {
        asm volatile("st.shared.u32 [%0], %1;" :: "r"(eps), "r"(t0) : "memory");
        asm volatile("st.shared.u32 [%0], %1;" :: "r"(eps + 4), "r"(t3) : "memory");
        mbar_arrive(epb);
        if (b < 8) { red_relaxed(&scr->sync[96], 1); red_relaxed(&scr->sync[128], 1); }
      }
      __syncwarp();
      mbar_wait(prog, 0);
      spin_clks(SYNC_D);
      const uint32_t tref = wait_ge_time<SYNC_G>(&scr->sync[160], t5) + SYNC_NS;
      PROF_W(8, lane == 0);
      if (elect_one()) {
        const uint32_t g0 = gtime();
        uint32_t g1 = g0;
        for (int it = 0; it < 64 && g1 == g0; it++) g1 = gtime();
        asm volatile("st.shared.u32 [%0], %1;" :: "r"(eps + 12), "r"(clk32() + (max(min((int)(tref - g1), 4096), -4096) * 107 >> 6)) : "memory");
        mbar_arrive(go);
        PROF_T(1);
        sleep_until(lds32(eps + 12), H0POLL);
        wait_ge(&scr->sync[0], t0); fence_async_global(); mbar_arrive(flh);
        PROF_T(17);
        mbar_wait(b >= 8 ? full2 : go, 0);
        sleep_until(lds32(eps + 12), GO_CLK);
        wait_ge(&scr->sync[32], t1); fence_async_global(); mbar_arrive(flh);
        mbar_wait(flu, 0);
        const uint32_t cu = clk32();
        sleep_until(cu, U1POLL);
        wait_ge(&scr->sync[128], t4); fence_async_global(); mbar_arrive(flu + 8);
        PROF_T(27);
        if (OAFT) spin_clks(OPOLL); else sleep_until(cu, OPOLL);
        wait_ge(&scr->sync[64], t2); fence_async_global(); mbar_arrive(flo);
        PROF_T(23);
      }
    }
  } else if (warp >= 8) {
    const int wq = warp - 8, b = cta_id();
    const bool has_g2 = b >= 8;
    uint32_t bias[16];
#pragma unroll
    for (int j = 0; j < 16; j++) asm volatile("ld.global.nc.u32 %0, [%1];" : "=r"(bias[j]) : "l"(b1 + (has_g2 ? tile_f(b) : 0) * 128 + 8 * j + 2 * (lane & 3)));
    {
      const int hl = lane & 15;
#pragma unroll 1
      for (int rr = 0; rr < 2; rr++) {
        mbar_wait(prepl + 8 * rr, 0);
        PROF_W(28, tid == 256 && rr == 0);
        const int row = rr * 8 + wq * 2 + (lane >> 4);
        const uint32_t ra = sb + XROW_OFF + row * (D_ * 2) + hl * 16;
        float v[40], sum = 0.f, sum2 = 0.f;
#pragma unroll
        for (int i = 0; i < 5; i++) {
          const uint4 t = lds128(ra + 256 * i);
          v[8 * i] = bf_lo(t.x); v[8 * i + 1] = bf_hi(t.x); v[8 * i + 2] = bf_lo(t.y); v[8 * i + 3] = bf_hi(t.y);
          v[8 * i + 4] = bf_lo(t.z); v[8 * i + 5] = bf_hi(t.z); v[8 * i + 6] = bf_lo(t.w); v[8 * i + 7] = bf_hi(t.w);
        }
#pragma unroll
        for (int i = 0; i < 40; i += 2) { sum += v[i]; sum2 += v[i + 1]; }
        sum += sum2;
#pragma unroll
        for (int o = 8; o > 0; o >>= 1) sum += __shfl_xor_sync(~0u, sum, o);
        mbar_arrive_if(xrd, rr == 1 && lane == 0);
        const float mean = sum * (1.f / D_);
        float var = 0.f, var2 = 0.f;
#pragma unroll
        for (int i = 0; i < 40; i += 2) { const float c0 = v[i] - mean, c1 = v[i + 1] - mean; var = fmaf(c0, c0, var); var2 = fmaf(c1, c1, var2); }
        var += var2;
#pragma unroll
        for (int o = 8; o > 0; o >>= 1) var += __shfl_xor_sync(~0u, var, o);
        const float rstd = rsqrtf(var * (1.f / D_) + 1e-5f), sh = -mean * rstd;
        __nv_bfloat16* hrow = scr->h + (size_t)(rr * (S_ / 2 - 8) + b * 8 + row) * D_ + hl * 8;
        float dot = 0.f, dot2 = 0.f;
        const uint32_t ch = clk32() + wq * (HP / 4);
#pragma unroll
        for (int i = 0; i < 5; i++) {
          if (HP) sleep_until(ch, i * HP); else sched_fence(zero);
          stg128(hrow + 128 * i, make_uint4(pack_bf16(fmaf(v[8 * i], rstd, sh), fmaf(v[8 * i + 1], rstd, sh)), pack_bf16(fmaf(v[8 * i + 2], rstd, sh), fmaf(v[8 * i + 3], rstd, sh)),
                                            pack_bf16(fmaf(v[8 * i + 4], rstd, sh), fmaf(v[8 * i + 5], rstd, sh)), pack_bf16(fmaf(v[8 * i + 6], rstd, sh), fmaf(v[8 * i + 7], rstd, sh))));
          if (i == 4) { if (rr == 0) bar_arrive<9, 160>(); else bar_arrive<10, 160>(); }
          const uint4 t = lds128(sb + GW_OFF + (hl + 16 * i) * 16);
          dot = fmaf(v[8 * i], bf_lo(t.x), dot); dot2 = fmaf(v[8 * i + 1], bf_hi(t.x), dot2); dot = fmaf(v[8 * i + 2], bf_lo(t.y), dot); dot2 = fmaf(v[8 * i + 3], bf_hi(t.y), dot2);
          dot = fmaf(v[8 * i + 4], bf_lo(t.z), dot); dot2 = fmaf(v[8 * i + 5], bf_hi(t.z), dot2); dot = fmaf(v[8 * i + 6], bf_lo(t.w), dot); dot2 = fmaf(v[8 * i + 7], bf_hi(t.w), dot2);
        }
        PROF_W(18, tid == 256 && rr == 0);
        dot += dot2;
#pragma unroll
        for (int o = 8; o > 0; o >>= 1) dot += __shfl_xor_sync(~0u, dot, o);
        const float gt = rcp(1.f + ex2(-1.4426950408889634f * dot));
        asm volatile("{\n.reg .pred p;\nsetp.eq.b32 p, %2, 0;\n@p st.shared.f32 [%0], %1;\n}" :: "r"(sb + GV_OFF + row * 4), "f"(gt), "r"(hl) : "memory");
      }
      fence_async_smem();
      __syncwarp();
      mbar_arrive_if(prepd, lane == 0);
      PROF_W(62, tid == 256);
    }
    if (!has_g2) {
      const int lr = lane & 7, m = lane >> 3, nt_ = (107 - b) >> 3;
      mbar_wait(full2, 0);
      const uint32_t cw = clk32();
#pragma unroll 1
      for (int j = wq; j < nt_; j += 4) {
        uint32_t r[16][4];
        const uint32_t ta = sb + j * 8192 + lr * 128;
#pragma unroll
        for (int i = 0; i < 16; i++) ldsm4t(ta + ((i >> 2) * 2 + (m & 1)) * 1024 + (((2 * (i & 3) + (m >> 1)) ^ lr) << 4), r[i][0], r[i][1], r[i][2], r[i][3]);
        __syncwarp();
#pragma unroll
        for (int i = 0; i < 16; i++) stsm4(sb + j * 8192 + ((i >> 2) * 2 + (m & 1)) * 1024 + (2 * (i & 3) + (m >> 1)) * 128 + lr * 16, r[i][0], r[i][1], r[i][2], r[i][3]);
        fence_async_smem();
        __syncwarp();
        sleep_until(cw, j * WOP);
        const int t = b + 8 * j, kt = t / 10;
        if (lane == 0) tma_store3(&maps.ust, sb + j * 8192, 0, (t - kt * 10) * 8, kt * 8);
        __syncwarp();
      }
      if (lane == 0) { bulk_commit(); bulk_wait0(); mbar_arrive(wod); }
      __syncwarp();
      mbar_wait(epb, 0);
      publish(&scr->sync[64], lane, 4);
      PROF_W(31, tid == 256);
    } else {
      float acc[64];
#pragma unroll
      for (int j = 0; j < 16; j++) {
        asm volatile("shl.b32 %0, %1, 16;" : "=f"(acc[4 * j]) : "r"(bias[j]));
        asm volatile("and.b32 %0, %1, 0xffff0000;" : "=f"(acc[4 * j + 1]) : "r"(bias[j]));
        asm volatile("prmt.b32 %0, %1, 0, 0x1044;" : "=f"(acc[4 * j + 2]) : "r"(bias[j]));
        asm volatile("prmt.b32 %0, %1, 0, 0x3244;" : "=f"(acc[4 * j + 3]) : "r"(bias[j]));
      }
      const bool rel = tid == 256;
      const uint64_t dA0 = make_desc(sb + g2_slot(1), 8192, 1024), dB0 = make_desc(sb + g2_slot(1) + 8192, 8192, 1024);
      char* up = (char*)scr->bcat + ((size_t)(80 + tile_f(b) * 16) * D_ + tile_d(b) * 64 + wq * 16) * 16 + lane * 4 + zero;
      asm volatile("" : "+l"(up));
      mbar_wait(go, 0);
      const uint32_t cref = lds32(eps + 12);
      mbar_wait(full2, 0);
      mbar_wait(full2 + 8, 0);
      PROF_W(3, tid == 256);
      sleep_until(cref, GO_CLK - 150);
      spin_until(cref, GO_CLK);
      PROF_W(24, tid == 256);
      wg_fence();
#pragma unroll
      for (int k = 0; k < 4; k++) wgmma_n128_ta1_tb1(acc, dA0 + 7 * (G2_SLOT >> 4) + k * 128, dB0 + 7 * (G2_SLOT >> 4) + k * 128, 1);
      wg_commit();
#pragma unroll 1
      for (int kb = 1; kb < 32; kb++) {
        const int i = (kb + 7) & 7;
        const uint64_t da = dA0 + i * (G2_SLOT >> 4), db = dB0 + i * (G2_SLOT >> 4);
        wg_fence();
#pragma unroll
        for (int k = 0; k < 4; k++) wgmma_n128_ta1_tb1(acc, da + k * 128, db + k * 128, 1);
        wg_commit();
        if (kb < 31) mbar_wait(full2 + 8 * ((kb + 1) & 7), ((kb + 1) >> 3) & 1);
        wg_wait<1>();
        mbar_arrive_if(empty2 + 8 * i, rel);
      }
      wg_wait<0>();
      mbar_arrive_if(empty2 + 8 * 7, rel);
      PROF_W(4, tid == 256);
      {
        constexpr int CH = UCH, NS = 32 / CH;
        float z[32];
#pragma unroll
        for (int i = -1; i <= NS; i++) {
          if (i >= 0 && i < NS) {
#pragma unroll
            for (int e = 0; e < CH; e++) z[CH * i + e] = tanh_fast(z[CH * i + e]);
          }
          if (i + 1 < NS) {
#pragma unroll
            for (int e = 0; e < CH; e++) z[CH * (i + 1) + e] = pin(gelu_arg(acc[CH * (i + 1) + e]));
          }
          if (i >= 1) {
#pragma unroll
            for (int e = CH * (i - 1); e < CH * i; e += 2)
              stg32(up + (e >> 2) * (D_ * 16) + (e & 2) * 64, pack_bf16(fmaf(acc[e], z[e], acc[e]), fmaf(acc[e + 1], z[e + 1], acc[e + 1])));
          }
          if (i >= 0 && i < NS - 1) sched_fence(zero);
        }
      }
      bar_arrive<6, 160>();
      PROF_W(20, tid == 256);
      mbar_arrive_if(gate, lane == 0);
      mbar_wait(xchd, 0);
      const uint32_t us = sb + XCH_OFF + (lane >> 4) * 1024 + wq * 256 + (lane & 15) * 16;
#pragma unroll
      for (int j = 0; j < 8; j += 2) {
        const int c = 32 + 4 * j;
        stsm4(us + j * 1024, pack_bf16(gelu2(acc[c]), gelu2(acc[c + 1])), pack_bf16(gelu2(acc[c + 2]), gelu2(acc[c + 3])),
              pack_bf16(gelu2(acc[c + 4]), gelu2(acc[c + 5])), pack_bf16(gelu2(acc[c + 6]), gelu2(acc[c + 7])));
      }
      fence_async_smem();
      bar_arrive<7, 160>();
    }
  } else {
    asm volatile("setmaxnreg.inc.sync.aligned.u32 168;");
    const int wg = warp >> 2, wq = warp & 3;
    const bool leader = (tid & 127) == 0;
    uint32_t bb;
    {
      uint32_t q[10][2], k[3][10], v[3][10];
      {
        const int b = cta_id(), mt = tile_m(b), hg = tile_n(b);
        const bool first = wq == 0 && mt == 0, remote = wq == 0 && mt > 0, odd = hg & 1;
        const uint32_t slot = sb + XCH_OFF + (wg * 3 + wq) * 2560 + lane * 16;
        uint4* const halo = scr->halo + ((mt * 8 + hg) * 2 + wg) * 224 + lane;
        float acc[96], acct[24];
        const uint64_t dA0 = make_desc(sb + wg * 8192, 16, 1024), dB0 = make_desc(sb + 16384, 4096, 1024);
        const uint64_t dT0 = make_desc(sb + 16384 + 24576, 1024, 256) | (3ull << 62);
#pragma unroll 1
        for (int hb = 0; hb < 20; hb++) {
          const int kb = hb >> 1, st = (kb + 2) & 3, hf = hb & 1;
          if (hb == 0) mbar_wait(half0, 0);
          else if (!hf || hb == 1) mbar_wait(full1 + 8 * st, (kb >> 2) & 1);
          PROF_W(32 + kb, tid == 0 && !hf);
          const uint64_t da = dA0 + st * (G1_STAGE >> 4) + hf * 4, db = dB0 + st * (G1_STAGE >> 4) + hf * 768, dtl = dT0 + st * (G1_STAGE >> 4) + hf * 192;
          wg_fence();
#pragma unroll
          for (int kk = 0; kk < 2; kk++) { wgmma_n192_ta0_tb1(acc, da + kk * 2, db + kk * 128, kk | hb); wgmma_n48_ta0_tb1(acct, da + kk * 2, dtl + kk * 32, kk | hb); }
          wg_commit();
          wg_wait<1>();
          mbar_arrive_if(empty1 + 8 * ((kb + 1) & 3), leader && !hf && hb > 0);
        }
        wg_wait<0>();
        mbar_arrive_if(empty1 + 8 * 3, leader);
        PROF_W(2 + 14 * wg, leader);
        {
          const __nv_bfloat16* bp = b2 + mt * 128 + warp * 16 + (lane >> 2);
          asm volatile("{\n.reg .u16 a, c;\nld.global.nc.u16 a, [%1];\nld.global.nc.u16 c, [%1 + 16];\nmov.b32 %0, {a, c};\n}" : "=r"(bb) : "l"(bp));
        }
        const uint32_t cs = clk32() + ((3 - wq) * 2 + wg) * XCHP;
        if (odd) pack_qkv<true>(acc, acct, q, k, v); else pack_qkv<false>(acc, acct, q, k, v);
        mbar_wait(epb, 0);
        const unsigned ep = lds32(eps);
        sleep_until(cs, XCH0);
#pragma unroll
        for (int g = 0; g < 10; g++) v[2][g] = movm_t(v[2][g]);
        if (wq < 3) {
          sts128(slot, make_uint4(k[2][0], k[2][1], k[2][3], k[2][4])); sts128(slot + 512, make_uint4(k[2][5], k[2][6], k[2][8], k[2][9]));
          sts128(slot + 1024, make_uint4(v[2][0], v[2][1], v[2][3], v[2][4])); sts128(slot + 1536, make_uint4(v[2][5], v[2][6], v[2][8], v[2][9]));
          sts128(slot + 2048, make_uint4(k[2][2], k[2][7], v[2][2], v[2][7]));
        } else if (mt < 15) {
          st_pkt(halo, k[2][0], k[2][1], k[2][2], ep); st_pkt(halo + 32, k[2][5], k[2][6], k[2][7], ep);
          st_pkt(halo + 64, k[2][3], k[2][4], v[2][2], ep); st_pkt(halo + 96, k[2][8], k[2][9], v[2][7], ep);
          st_pkt(halo + 128, v[2][0], v[2][1], v[2][8], ep); st_pkt(halo + 160, v[2][3], v[2][4], v[2][9], ep);
          st_pkt(halo + 192, v[2][5], v[2][6], ep, ep);
        }
        if (wg == 0) bar_sync<1, 128>(); else bar_sync<2, 128>();
        sleep_until(cs, remote ? XCH2 : XCH1);
#pragma unroll
        for (int g = 0; g < 10; g++) v[1][g] = movm_t(v[1][g]);
        if (remote) {
          uint4 e[7];
          for (int it = 0;; it++) {
#pragma unroll
            for (int i = 0; i < 7; i++) e[i] = ld_pkt(halo - 8 * 2 * 224 + 32 * i);
            const bool ok = e[0].w == ep && e[1].w == ep && e[2].w == ep && e[3].w == ep && e[4].w == ep && e[5].w == ep && e[6].z == ep && e[6].w == ep;
            if (__all_sync(~0u, ok) || it > (1 << 20)) break;
          }
          k[0][0] = e[0].x; k[0][1] = e[0].y; k[0][2] = e[0].z; k[0][5] = e[1].x; k[0][6] = e[1].y; k[0][7] = e[1].z;
          k[0][3] = e[2].x; k[0][4] = e[2].y; v[0][2] = e[2].z; k[0][8] = e[3].x; k[0][9] = e[3].y; v[0][7] = e[3].z;
          v[0][0] = e[4].x; v[0][1] = e[4].y; v[0][8] = e[4].z; v[0][3] = e[5].x; v[0][4] = e[5].y; v[0][9] = e[5].z;
          v[0][5] = e[6].x; v[0][6] = e[6].y;
        } else {
          const uint32_t a = first ? slot : slot - 2560;
          const uint4 e0 = lds128(a), e1 = lds128(a + 512), e2 = lds128(a + 1024), e3 = lds128(a + 1536), e4 = lds128(a + 2048);
          k[0][0] = e0.x; k[0][1] = e0.y; k[0][3] = e0.z; k[0][4] = e0.w; k[0][5] = e1.x; k[0][6] = e1.y; k[0][8] = e1.z; k[0][9] = e1.w;
          v[0][0] = e2.x; v[0][1] = e2.y; v[0][3] = e2.z; v[0][4] = e2.w; v[0][5] = e3.x; v[0][6] = e3.y; v[0][8] = e3.z; v[0][9] = e3.w;
          k[0][2] = e4.x; k[0][7] = e4.y; v[0][2] = e4.z; v[0][7] = e4.w;
        }
        mbar_arrive_if(xchd, lane == 0);
        PROF_W(48 + warp, lane == 0);
        attention(q, k, v, first, lane, zero, b >= 8 ? gate : prepd, fresh(sb + OSTG_OFF + (lane >> 4) * 2048 + ((wq * 16 + (lane & 15)) * 2 + wg) * 16, zero));
      }
      fence_async_smem();
      bar_sync<4, 288>();
      PROF_W(56 + warp, lane == 0 && warp < 6);
    }
    {
      float accA[40], accY[40];
      const int b = cta_id(), row0 = tile_m(b) * 128 + warp * 16;
      const uint64_t dAk = make_desc(sb + wg * 1024, 2048, 128) & ~(3ull << 62), dAm = make_desc(sb + wg * 8192, 8192, 1024), dB0 = make_desc(sb + 16384, 1280, 128) & ~(3ull << 62);
      {
        const uint64_t da = dAk + (OSTG_OFF >> 4), db = make_desc(sb + (P2N - 1) * P2_SLOT, 10240, 1024);
        mbar_wait(bown, 0);
        wg_fence();
#pragma unroll
        for (int kk = 0; kk < 5; kk++) wgmma_n80_ta0_tb1(accA, da + kk * 256, db + kk * 128, kk);
        wg_commit();
        wg_wait<0>();
        mbar_arrive_if(ownd, leader);
        PROF_W(63, tid == 0);
      }
      int i = 0, ph = 0, prev = 0;
#pragma unroll 1
      for (int kb = 0; kb < 24; kb++) {
        mbar_wait(full3 + 8 * i, ph);
        if (kb == 0) PROF_W(26, tid == 0);
        const uint64_t da = dAm + i * (P2_SLOT >> 4), db = dB0 + i * (P2_SLOT >> 4);
        wg_fence();
#pragma unroll
        for (int kk = 0; kk < 4; kk++) wgmma_n80_ta1_tb0(accY, da + kk * 128, db + kk * 160, kk | kb);
        wg_commit();
        wg_wait<1>();
        mbar_arrive_if(empty3 + 8 * prev, leader && kb > 0);
        prev = i;
        if (++i == P2N) { i = 0; ph ^= 1; }
      }
      PROF_W(6, tid == 0);
      mbar_wait(full3 + 8 * i, ph);
      const float g0 = __ldcg(scr->gate + row0 * 4 + (lane >> 2)), g1 = __ldcg(scr->gate + row0 * 4 + 32 + (lane >> 2));
      const int own = b & 3;
#pragma unroll 1
      for (int k2 = 0; k2 < 5; k2++) {
#pragma unroll
        for (int u = 0; u < 2; u++) {
          mbar_wait(full3 + 8 * i, ph);
          if (k2 == 0 && u == 0) PROF_W(25, tid == 0);
          const uint64_t da = dAk + i * (P2_SLOT >> 4), db = dB0 + i * (P2_SLOT >> 4);
          wg_fence();
#pragma unroll
          for (int kk = 0; kk < 4 - u; kk++) {
            const int ks = kk + (u && kk >= own);
            wgmma_n80_ta0_tb0(accA, da + ks * 256, db + ks * 160, 1);
          }
          wg_commit();
          wg_wait<1>();
          mbar_arrive_if(empty3 + 8 * prev, leader);
          prev = i;
          if (++i == P2N) { i = 0; ph ^= 1; }
        }
      }
      const int odd = b & 1, rw = lane & 15;
      const uint32_t sta = sb + OSTG_OFF + warp * 2048, stb = sb + OSTG_OFF + 16384 + warp * 512;
      const uint32_t aa = sta + rw * 128, sw = (lane >> 4) ^ (lane & 7), ab = stb + rw * 32 + ((((lane >> 4) ^ (lane >> 2)) & 1) << 4);
      uint32_t adr[5];
#pragma unroll
      for (int p = 0; p < 5; p++) adr[p] = p == (odd ? 0 : 4) ? ab : aa + ((sw ^ (2 * (p - odd))) << 4);
      asm volatile("" : "+r"(adr[0]), "+r"(adr[1]), "+r"(adr[2]), "+r"(adr[3]), "+r"(adr[4]));
      wg_wait<0>();
      PROF_W(7, tid == 0);
      const float h0 = 1.f - g0, h1 = 1.f - g1, c0 = h0 * bf_lo(bb), c1 = h1 * bf_hi(bb), y0 = 0.5f * h0, y1 = 0.5f * h1;
#pragma unroll
      for (int j = 0; j < 10; j += 2) {
        uint32_t r[4];
#pragma unroll
        for (int t = 0; t < 2; t++) {
          const int c = 4 * (j + t);
          r[2 * t] = pack_bf16(fmaf(g0, accA[c], fmaf(y0, accY[c], c0)), fmaf(g0, accA[c + 1], fmaf(y0, accY[c + 1], c0)));
          r[2 * t + 1] = pack_bf16(fmaf(g1, accA[c + 2], fmaf(y1, accY[c + 2], c1)), fmaf(g1, accA[c + 3], fmaf(y1, accY[c + 3], c1)));
        }
        stsm4(adr[j >> 1], r[0], r[1], r[2], r[3]);
      }
      fence_async_smem();
      __syncwarp();
      if (elect_one()) {
        tma_store2(&maps.outa, sta, w_main(tile_n(b)), row0);
        tma_store2(&maps.outb, stb, w_tail(tile_n(b)), row0);
        bulk_commit(); bulk_wait0_read();
        if (warp == 0) PROF_T(15);
      }
    }
  }
}

typedef CUresult (*EncodeFn)(CUtensorMap*, CUtensorMapDataType, cuuint32_t, void*, const cuuint64_t*, const cuuint64_t*, const cuuint32_t*,
                             const cuuint32_t*, CUtensorMapInterleave, CUtensorMapSwizzle, CUtensorMapL2promotion, CUtensorMapFloatOOBfill);

void make_map(EncodeFn fn, CUtensorMap* m, const void* ptr, int rank, uint64_t d0, uint64_t d1, uint64_t d2, uint64_t s1, uint64_t s2,
              uint32_t b0, uint32_t b1, uint32_t b2, CUtensorMapSwizzle sw = CU_TENSOR_MAP_SWIZZLE_128B,
              CUtensorMapL2promotion promo = CU_TENSOR_MAP_L2_PROMOTION_L2_128B) {
  cuuint64_t dims[3] = {d0, d1, d2}, strides[2] = {s1, s2};
  cuuint32_t box[3] = {b0, b1, b2}, es[3] = {1, 1, 1};
  fn(m, CU_TENSOR_MAP_DATA_TYPE_BFLOAT16, rank, const_cast<void*>(ptr), dims, strides, box, es, CU_TENSOR_MAP_INTERLEAVE_NONE,
     sw, promo, CU_TENSOR_MAP_FLOAT_OOB_FILL_NONE);
}

}

extern "C" void kernel_launch(void* const* d_in, const int* in_sizes, int n_in, void* d_out, int out_size) {
  const __nv_bfloat16* x = (const __nv_bfloat16*)d_in[0];
  const __nv_bfloat16* wqkv = (const __nv_bfloat16*)d_in[1];
  const __nv_bfloat16* wo = (const __nv_bfloat16*)d_in[2];
  const __nv_bfloat16* w1 = (const __nv_bfloat16*)d_in[4];
  const __nv_bfloat16* b1 = (const __nv_bfloat16*)d_in[5];
  const __nv_bfloat16* w2 = (const __nv_bfloat16*)d_in[6];
  const __nv_bfloat16* b2 = (const __nv_bfloat16*)d_in[7];
  const __nv_bfloat16* gate_w = (const __nv_bfloat16*)d_in[8];

  void* fnp = nullptr; cudaDriverEntryPointQueryResult qr;
  cudaGetDriverEntryPoint("cuTensorMapEncodeTiled", &fnp, cudaEnableDefault, &qr);
  EncodeFn fn = (EncodeFn)fnp;
  Scratch* scr; cudaGetSymbolAddress((void**)&scr, g_scr);
  void *ph = scr->h, *pb = scr->bcat;
  Maps maps;
  make_map(fn, &maps.x, x, 3, D_, S_ / 2, 2, 2 * D_ * 2, D_ * 2, 64, 64, 2);
  make_map(fn, &maps.wa, wqkv, 3, D_, D_, 3, 3 * D_ * 2, D_ * 2, 64, 32, 3);
  make_map(fn, &maps.wb, wqkv, 3, D_, D_, 3, 3 * D_ * 2, D_ * 2, 16, 32, 3, CU_TENSOR_MAP_SWIZZLE_32B);
  make_map(fn, &maps.h, ph, 2, D_, S_, 1, D_ * 2, 0, 64, 64, 1);
  make_map(fn, &maps.w1, w1, 3, 64, S_, F_ / 64, F_ * 2, 128, 64, 64, 2);
  make_map(fn, &maps.bc, pb, 3, 64, D_ / 8, KCAT / 8, 128, D_ * 16, 64, 10, 8, CU_TENSOR_MAP_SWIZZLE_NONE);
  make_map(fn, &maps.w2, w2, 3, 64, F_, S_ / 64, S_ * 2, 128, 64, 64, 2);
  make_map(fn, &maps.ust, pb, 3, 64, D_ / 8, KCAT / 8, 128, D_ * 16, 64, 8, 8, CU_TENSOR_MAP_SWIZZLE_NONE);
  make_map(fn, &maps.outa, d_out, 2, D_, S_, 1, D_ * 2, 0, 64, 16, 1);
  make_map(fn, &maps.outb, d_out, 2, D_, S_, 1, D_ * 2, 0, 16, 16, 1, CU_TENSOR_MAP_SWIZZLE_32B);
  make_map(fn, &maps.wo, wo, 3, D_, 80, 8, D_ * 2, 80 * D_ * 2, 64, 16, 4);
  make_map(fn, &maps.woa, wo, 2, D_, D_, 1, D_ * 2, 0, 64, 80, 1);
  make_map(fn, &maps.wob, wo, 2, D_, D_, 1, D_ * 2, 0, 16, 80, 1);
  cudaFuncSetAttribute(fused_kernel, cudaFuncAttributeMaxDynamicSharedMemorySize, SMEM_BYTES);
  fused_kernel<<<NCTA, NTHREADS, SMEM_BYTES>>>(scr, x, w1, b1, b2, gate_w, 0u, maps);
}
```
